```python
import torch

def _softmax(x, axis=-1):
    return torch.softmax(x, dim=axis)

def _gelu(x):
    return torch.nn.functional.gelu(x, approximate='tanh')

def _silu(x):
    return torch.nn.functional.silu(x)

def _sigmoid(x):
    return torch.sigmoid(x)

def _layernorm(x, axis=-1, eps=1e-05):
    m = x.mean(dim=axis, keepdim=True)
    v = x.var(dim=axis, keepdim=True, unbiased=False)
    return (x - m) / torch.sqrt(v + eps)

def _scatter_add(tgt, idx, src, axis=0):
    return tgt.clone().index_add_(axis, idx, src)

def _segment_sum(src, seg, n):
    out = torch.zeros((n,) + src.shape[1:], dtype=src.dtype)
    return out.index_add_(0, seg, src)

def _pad(x, pw):
    flat = tuple((v for pair in reversed(pw) for v in pair))
    return torch.nn.functional.pad(x, flat)
kernel_name = 'parallel_sum__ssm_conv_h3__mixer_gmlp__prompt'

def setup_inputs():

    _w = lambda a: (lambda t: t.to(torch.bfloat16) if t.is_floating_point() else t)(torch.as_tensor(a))

    def _A_setup():
        B, S, D = (1, 2048, 512)
        ks = 4
        return {'q': _w((lambda *s: torch.randn(*s, dtype=torch.bfloat16) * 0.05)(B, S, D)), 'k': _w((lambda *s: torch.randn(*s, dtype=torch.bfloat16) * 0.8)(B, S, D)), 'v': _w((lambda *s: torch.randn(*s, dtype=torch.bfloat16) * 0.8)(B, S, D)), 'shift_k': _w((lambda *s: torch.randn(*s, dtype=torch.bfloat16) * 0.8)(D, ks) * 0.5), 'ssm_k': _w((lambda *s: torch.randn(*s, dtype=torch.bfloat16) * 1.6)(D, S) * (1.0 / S ** 0.5)), 'ssm_D': _w((lambda *s: torch.randn(*s, dtype=torch.bfloat16) * 0.8)(D))}
    _A_in = _A_setup()

    def _B_setup():
        B, S, D, F = (1, 2048, 512, 1792)
        Fh = F // 2
        return {'x': _w((lambda *s: torch.randn(*s, dtype=torch.bfloat16) * 0.05)(B, S, D)), 'w_in': _w((lambda *s: torch.randn(*s, dtype=torch.bfloat16) * 0.4)(D, 2 * Fh)), 'w_sp': _w(0.01 * (lambda *s: torch.randn(*s, dtype=torch.bfloat16) * 0.4)(S, S)), 'b_sp': _w(1.0 + 0.01 * (lambda *s: torch.randn(*s, dtype=torch.bfloat16) * 0.05)(S)), 'w_out': _w((lambda *s: torch.randn(*s, dtype=torch.bfloat16) * 0.05)(Fh, D))}
    _B_in = _B_setup()
    return {'A_q': _A_in['q'], 'A_k': _A_in['k'], 'A_v': _A_in['v'], 'A_shift_k': _A_in['shift_k'], 'A_ssm_k': _A_in['ssm_k'], 'A_ssm_D': _A_in['ssm_D'], 'B_x': _B_in['x'], 'B_w_in': _B_in['w_in'], 'B_w_sp': _B_in['w_sp'], 'B_b_sp': _B_in['b_sp'], 'B_w_out': _B_in['w_out']}

def reference(A_q, A_k, A_v, A_shift_k, A_ssm_k, A_ssm_D, B_x, B_w_in, B_w_sp, B_b_sp, B_w_out):

    def _A_ref(q, k, v, shift_k, ssm_k, ssm_D):
        B, S, D = q.shape
        ks = shift_k.shape[-1]
        k_pad = _pad(k, ((0, 0), (ks - 1, 0), (0, 0)))
        k_shift = torch.zeros_like(k)
        for t in range(ks):
            k_shift = k_shift + k_pad[:, t:t + S, :] * shift_k[:, ks - 1 - t][None, None, :]
        kv = k_shift * v
        L = 2 * S
        kv_pad = _pad(kv, ((0, 0), (0, S), (0, 0)))
        kf_pad = _pad(ssm_k, ((0, 0), (0, S)))
        kv_f = (lambda x, axes=(-2, -1): torch.fft.rfft2(x.float(), dim=axes))(kv_pad[:, None, :, :], axes=(1, 2))
        kf_f = (lambda x, axes=(-2, -1): torch.fft.rfft2(x.float(), dim=axes))(kf_pad[:, None, :], axes=(1, 2))
        kf_f = (lambda x, *d: x.permute(*d))(kf_f, 1, 2, 0)
        y_f = kv_f * kf_f[None, :, :, :]
        y = (lambda x, s, axes=(-2, -1): torch.fft.irfft2(x, s=s, dim=axes).to(torch.bfloat16))(y_f, (1, L), axes=(1, 2))[:, 0, :S, :]
        y = y + kv * ssm_D[None, None, :]
        return q * y

    def _B_ref(x, w_in, w_sp, b_sp, w_out):
        B, S, D = x.shape
        F = w_in.shape[-1]
        Fh = F // 2
        z = _gelu(torch.einsum('bsd,df->bsf', x, w_in))
        z1 = z[..., :Fh].clone()
        z2 = _layernorm(z[..., Fh:], axis=-1)
        g = torch.einsum('ts,bsf->btf', w_sp, z2) + b_sp[None, :, None]
        return torch.einsum('bsf,fd->bsd', z1 * g, w_out)
    x = A_q
    xn = _layernorm(x, axis=-1)
    return x + _A_ref(xn, A_k, A_v, A_shift_k, A_ssm_k, A_ssm_D) + _B_ref(xn, B_w_in, B_w_sp, B_b_sp, B_w_out)
```

```cpp
#include <cuda_runtime.h>
#include <cuda.h>
#include <cuda_bf16.h>
#include <stdint.h>

namespace {

constexpr int S_ = 2048, D_ = 512, FH_ = 896, F_ = 1792;
constexpr unsigned GRID = 132;
#define LL_STEP0 3
#define LL_STEP1 5
#define XS_DELAY 0
#define LN_DELAY 700
#define RESUME_LATE 0
#define A_PRE 2
#define UK_GATE B_TAG
#define XLOOK 4
#define CS_STEP 4
#define XR_POS 1
#define C_POS 0
#define KV_AT 1
#define PAUSE_KV 0
#define HELP_DELAY 500
#define PAUSE_STEP 24
#define KV_AFTER_G1 1
#define CONV_E0 0
#define PRESIG 2
#define KV_POS 50
#define PF_GATE (B_FULLX + 7)
#define CS_DELAY 600
#define US_DT 300
#define BACKOFF 300
#define LN_GAP 0
#define LN_AFTER_KV 0
#define XQ 4
#define Y_STEP 4
#define GO_NS 1200
#define RES_STEP 7
#define SKEW 0
#define RES_STAG 0
#define US_GATE B_G2RUN
#define UK_DT 150
#define KV_DELAY 300
#define KV_WAIT B_Z1DONE
#define CONV_E1 4
#define PF_GATE0 (B_FULLX + 1)
#define PF_DT 400

constexpr uint32_t PAGE = 16384;
constexpr uint32_t CONV_OFF = 12 * PAGE;
constexpr uint32_t CONV_W = 8448;
constexpr uint32_t CS_OFF = CONV_OFF + 4 * CONV_W;
constexpr uint32_t LN_OFF = CS_OFF + 448;
constexpr uint32_t BAR_OFF = CS_OFF + 960;
constexpr uint32_t HB = 14336;
enum {
  B_FULLX = 0, B_FULLW = 8, B_FULLC = 12, B_FULLXQ = 13, B_FULLKV = 14,
  B_WOFREE = 15, B_X01 = 16, B_CFREE = 17, B_ZSET = 18, B_FULLA = 19, B_FULLB = 25,
  B_DONE2 = 30, B_KVC = 36, B_DONEH = 37, B_FULLW2 = 46, B_LNST = 50, B_LN = 51, B_G2RUN = 52, B_CS = 53, B_FULLY = 55,
  B_FULLU = 57, B_G1DONE = 58, B_G2DONE = 59, B_CONVMMA = 60, B_P1DONE = 61, B_Z1DONE = 62, B_PAUSE = 63, B_RESUME = 64,
  B_TAG = 65, B_EMPTYW = 66, B_ZST = 70, B_HST = 72, B_FULLWO = 74, B_CONVFREE = 76, B_USTG = 77,
  B_FULLH = 78, B_SKEW = 75, B_HFREE = 94, B_COUNT = 95
};
constexpr uint32_t TAG_OFF = BAR_OFF + B_COUNT * 8;
constexpr uint32_t TS_OFF = TAG_OFF + 8;
constexpr uint32_t SMEM_BYTES = TS_OFF;
static_assert(SMEM_BYTES <= 232448, "smem");

__device__ unsigned g_ticket;
__device__ unsigned g_cntU[4 * 32];
__device__ __align__(8) unsigned g_cntZ[64];
__device__ unsigned g_cntH[16 * 32];
__device__ ulonglong2 g_xs[S_];
__device__ ulonglong2 g_cs[8 * 8 * 64];
__device__ ulonglong2 g_cs1[FH_ / 2];
__device__ unsigned long long g_ln[S_ * 8];
__device__ __align__(128) uint4 g_u[D_ * S_ / 8];
__device__ __align__(128) uint4 g_z2[8 * 32 * HB / 16];
__device__ __align__(128) uint4 g_h[16 * 16 * HB / 16];
__device__ __align__(128) uint4 g_y[D_ * S_ / 8];
#define TS(n) do {} while (0)

__device__ __forceinline__ uint32_t smem_u32(const void* p) { return (uint32_t)__cvta_generic_to_shared(p); }
__device__ __forceinline__ void mbar_init(uint32_t bar, uint32_t cnt) {
  asm volatile("mbarrier.init.shared::cta.b64 [%0], %1;" ::"r"(bar), "r"(cnt) : "memory");
}
__device__ __forceinline__ void mbar_expect(uint32_t bar, uint32_t bytes) {
  asm volatile("mbarrier.arrive.expect_tx.shared::cta.b64 _, [%0], %1;" ::"r"(bar), "r"(bytes) : "memory");
}
__device__ __forceinline__ void mbar_arrive(uint32_t bar) {
  asm volatile("mbarrier.arrive.shared::cta.b64 _, [%0];" ::"r"(bar) : "memory");
}
__device__ __forceinline__ void mbar_wait(uint32_t bar, uint32_t parity) {
  asm volatile("{ .reg .pred p; .reg .u32 c; mov.u32 c, 0;\n"
               "W_LOOP: mbarrier.try_wait.parity.shared::cta.b64 p, [%0], %1;\n"
               "@p bra W_DONE;\n"
               "add.u32 c, c, 1; setp.lt.u32 p, c, 1048576;\n"
               "@p bra W_LOOP;\n"
               "{ .reg .b64 z; mov.b64 z, 0; st.global.u32 [z], c; }\n"
               "W_DONE: }" ::"r"(bar), "r"(parity) : "memory");
}
__device__ __forceinline__ void spin_guard(int& it) {
  ++it;
  asm volatile("{ .reg .pred p; .reg .b64 z; mov.b64 z, 0; setp.gt.s32 p, %0, 1048576; @p st.global.u32 [z], %0; }" ::"r"(it));
}
#define SPIN_GUARD(it, id) spin_guard(it)
__device__ __forceinline__ void tma2d(uint32_t dst, const CUtensorMap* m, int c0, int c1, uint32_t bar) {
  asm volatile("cp.async.bulk.tensor.2d.shared::cluster.global.mbarrier::complete_tx::bytes [%0], [%1, {%3,%4}], [%2];"
               ::"r"(dst), "l"(m), "r"(bar), "r"(c0), "r"(c1) : "memory");
}
__device__ __forceinline__ void tma2d_prefetch(const CUtensorMap* m, int c0, int c1) {
  asm volatile("cp.async.bulk.prefetch.tensor.2d.L2.global.tile [%0, {%1,%2}];" ::"l"(m), "r"(c0), "r"(c1) : "memory");
}
__device__ __forceinline__ void tma2d_store(const CUtensorMap* m, int c0, int c1, uint32_t src) {
  asm volatile("cp.async.bulk.tensor.2d.global.shared::cta.bulk_group [%0, {%1,%2}], [%3];"
               ::"l"(m), "r"(c0), "r"(c1), "r"(src) : "memory");
}
__device__ __forceinline__ void bulk_load(uint32_t dst, const void* src, uint32_t bytes, uint32_t bar) {
  asm volatile("cp.async.bulk.shared::cluster.global.mbarrier::complete_tx::bytes [%0], [%1], %2, [%3];"
               ::"r"(dst), "l"(src), "r"(bytes), "r"(bar) : "memory");
}
__device__ __forceinline__ void bulk_load_mc(uint32_t dst, const void* src, uint32_t bytes, uint32_t bar) {
  asm volatile("cp.async.bulk.shared::cluster.global.mbarrier::complete_tx::bytes.multicast::cluster [%0], [%1], %2, [%3], %4;"
               ::"r"(dst), "l"(src), "r"(bytes), "r"(bar), "h"((uint16_t)3) : "memory");
}
__device__ __forceinline__ void mbar_arrive_cta(uint32_t bar, uint32_t cta) {
  asm volatile("{ .reg .b32 r; mapa.shared::cluster.u32 r, %0, %1; mbarrier.arrive.shared::cluster.b64 _, [r]; }"
               ::"r"(bar), "r"(cta) : "memory");
}
__device__ __forceinline__ void cluster_arrive() { asm volatile("barrier.cluster.arrive.relaxed;" ::: "memory"); }
__device__ __forceinline__ void cluster_wait() { asm volatile("barrier.cluster.wait.acquire;" ::: "memory"); }
__device__ __forceinline__ void bulk_store(void* dst, uint32_t src, uint32_t bytes) {
  asm volatile("cp.async.bulk.global.shared::cta.bulk_group [%0], [%1], %2;" ::"l"(dst), "r"(src), "r"(bytes) : "memory");
}
__device__ __forceinline__ void bulk_prefetch(const void* src, uint32_t bytes) {
  asm volatile("cp.async.bulk.prefetch.L2.global [%0], %1;" ::"l"(src), "r"(bytes) : "memory");
}
__device__ __forceinline__ void bulk_commit() { asm volatile("cp.async.bulk.commit_group;" ::: "memory"); }
__device__ __forceinline__ void bulk_wait0() { asm volatile("cp.async.bulk.wait_group 0;" ::: "memory"); }
__device__ __forceinline__ void bulk_wait0_read() { asm volatile("cp.async.bulk.wait_group.read 0;" ::: "memory"); }
__device__ __forceinline__ void fence_async_smem() { asm volatile("fence.proxy.async.shared::cta;" ::: "memory"); }
__device__ __forceinline__ void fence_gpu() { asm volatile("fence.acq_rel.gpu;" ::: "memory"); }
__device__ __forceinline__ void bar_sync(int id, int n) { asm volatile("bar.sync %0, %1;" ::"r"(id), "r"(n) : "memory"); }
__device__ __forceinline__ bool bar_all(int id, int n, bool p) {
  uint32_t r;
  asm volatile("{ .reg .pred a, b; setp.ne.u32 a, %3, 0; bar.red.and.pred b, %1, %2, a; selp.u32 %0, 1, 0, b; }"
               : "=r"(r) : "r"(id), "r"(n), "r"((uint32_t)p) : "memory");
  return r;
}
__device__ __forceinline__ void bar_arrive(int id, int n) { asm volatile("bar.arrive %0, %1;" ::"r"(id), "r"(n) : "memory"); }
__device__ __forceinline__ void wg_fence() { asm volatile("wgmma.fence.sync.aligned;" ::: "memory"); }
__device__ __forceinline__ void wg_commit() { asm volatile("wgmma.commit_group.sync.aligned;" ::: "memory"); }
template <int N> __device__ __forceinline__ void wg_wait() { asm volatile("wgmma.wait_group.sync.aligned %0;" ::"n"(N) : "memory"); }
__device__ __forceinline__ uint64_t mkdesc(uint32_t addr, uint32_t lbo, uint32_t sbo, uint32_t sw) {
  return (uint64_t)((addr & 0x3FFFF) >> 4) | ((uint64_t)(lbo >> 4) << 16) | ((uint64_t)(sbo >> 4) << 32) | ((uint64_t)sw << 62);
}
__device__ __forceinline__ unsigned ld_rlx(const unsigned* p) {
  unsigned v; asm volatile("ld.relaxed.gpu.global.u32 %0, [%1];" : "=r"(v) : "l"(p) : "memory"); return v;
}
__device__ __forceinline__ void red_inc(unsigned* p) {
  asm volatile("red.relaxed.gpu.global.add.u32 [%0], 1;" ::"l"(p) : "memory");
}
__device__ __forceinline__ unsigned long long ld_rlx64(const unsigned long long* p) {
  unsigned long long v; asm volatile("ld.relaxed.gpu.global.b64 %0, [%1];" : "=l"(v) : "l"(p) : "memory"); return v;
}
__device__ __forceinline__ void st_rlx64(unsigned long long* p, unsigned long long v) {
  asm volatile("st.relaxed.gpu.global.b64 [%0], %1;" ::"l"(p), "l"(v) : "memory");
}
__device__ __forceinline__ ulonglong2 ld_ll(const ulonglong2* p) {
  ulonglong2 v; asm volatile("ld.relaxed.gpu.global.v2.b64 {%0,%1}, [%2];" : "=l"(v.x), "=l"(v.y) : "l"(p) : "memory"); return v;
}
__device__ __forceinline__ void st_ll(ulonglong2* p, float a, float b, unsigned tag) {
  unsigned long long x = ((unsigned long long)tag << 32) | __float_as_uint(a);
  unsigned long long y = ((unsigned long long)tag << 32) | __float_as_uint(b);
  asm volatile("st.relaxed.gpu.global.v2.b64 [%0], {%1,%2};" ::"l"(p), "l"(x), "l"(y) : "memory");
}
__device__ __forceinline__ bool ll_ok(const ulonglong2& v, unsigned tag) {
  return (unsigned)(v.x >> 32) == tag && (unsigned)(v.y >> 32) == tag;
}
__device__ __forceinline__ float bf_lo(uint32_t w) { return __uint_as_float(w << 16); }
__device__ __forceinline__ float bf_hi(uint32_t w) { return __uint_as_float(w & 0xffff0000u); }
__device__ __forceinline__ uint32_t pack_bf(float lo, float hi) {
  uint32_t r; asm("cvt.rn.bf16x2.f32 %0, %1, %2;" : "=r"(r) : "f"(hi), "f"(lo)); return r;
}
__device__ __forceinline__ uint32_t pack_bf_v(float lo, float hi) {
  uint32_t r; asm volatile("cvt.rn.bf16x2.f32 %0, %1, %2;" : "=r"(r) : "f"(hi), "f"(lo)); return r;
}
__device__ __forceinline__ uint32_t bfma2(uint32_t a, uint32_t b, uint32_t c) {
  uint32_t r; asm("fma.rn.bf16x2 %0, %1, %2, %3;" : "=r"(r) : "r"(a), "r"(b), "r"(c)); return r;
}
__device__ __forceinline__ uint32_t bmul2(uint32_t a, uint32_t b) {
  uint32_t r; asm("mul.rn.bf16x2 %0, %1, %2;" : "=r"(r) : "r"(a), "r"(b)); return r;
}
__device__ __forceinline__ uint32_t badd2(uint32_t a, uint32_t b) {
  uint32_t r; asm("add.rn.bf16x2 %0, %1, %2;" : "=r"(r) : "r"(a), "r"(b)); return r;
}
__device__ __forceinline__ float tanh_fast(float x) { float r; asm("tanh.approx.f32 %0, %1;" : "=f"(r) : "f"(x)); return r; }
__device__ __forceinline__ void stsm4(uint32_t a, uint32_t r0, uint32_t r1, uint32_t r2, uint32_t r3) {
  asm volatile("stmatrix.sync.aligned.m8n8.x4.shared.b16 [%0], {%1,%2,%3,%4};"
               ::"r"(a), "r"(r0), "r"(r1), "r"(r2), "r"(r3) : "memory");
}
__device__ __forceinline__ void stsm4t(uint32_t a, uint32_t r0, uint32_t r1, uint32_t r2, uint32_t r3) {
  asm volatile("stmatrix.sync.aligned.m8n8.x4.trans.shared.b16 [%0], {%1,%2,%3,%4};"
               ::"r"(a), "r"(r0), "r"(r1), "r"(r2), "r"(r3) : "memory");
}
__device__ __forceinline__ void ldsm4(uint32_t a, uint32_t& r0, uint32_t& r1, uint32_t& r2, uint32_t& r3) {
  asm volatile("ldmatrix.sync.aligned.m8n8.x4.shared.b16 {%0,%1,%2,%3}, [%4];" : "=r"(r0), "=r"(r1), "=r"(r2), "=r"(r3) : "r"(a) : "memory");
}
__device__ __forceinline__ void ldsm4t(uint32_t a, uint32_t& r0, uint32_t& r1, uint32_t& r2, uint32_t& r3) {
  asm volatile("ldmatrix.sync.aligned.m8n8.x4.trans.shared.b16 {%0,%1,%2,%3}, [%4];" : "=r"(r0), "=r"(r1), "=r"(r2), "=r"(r3) : "r"(a) : "memory");
}
__device__ __forceinline__ uint32_t lds32(uint32_t a) { uint32_t v; asm volatile("ld.shared.u32 %0, [%1];" : "=r"(v) : "r"(a)); return v; }
__device__ __forceinline__ uint2 lds64(uint32_t a) { uint2 v; asm volatile("ld.shared.v2.u32 {%0,%1}, [%2];" : "=r"(v.x), "=r"(v.y) : "r"(a)); return v; }
__device__ __forceinline__ uint4 lds128(uint32_t a) { uint4 v; asm volatile("ld.shared.v4.u32 {%0,%1,%2,%3}, [%4];" : "=r"(v.x), "=r"(v.y), "=r"(v.z), "=r"(v.w) : "r"(a)); return v; }
__device__ __forceinline__ void sts32(uint32_t a, uint32_t v) { asm volatile("st.shared.u32 [%0], %1;" ::"r"(a), "r"(v) : "memory"); }
__device__ __forceinline__ void sts64(uint32_t a, uint32_t x, uint32_t y) { asm volatile("st.shared.v2.u32 [%0], {%1,%2};" ::"r"(a), "r"(x), "r"(y) : "memory"); }
__device__ __forceinline__ void sts128(uint32_t a, uint32_t x, uint32_t y, uint32_t z, uint32_t w) {
  asm volatile("st.shared.v4.u32 [%0], {%1,%2,%3,%4};" ::"r"(a), "r"(x), "r"(y), "r"(z), "r"(w) : "memory");
}
__device__ __forceinline__ void mma16816(float (&c)[4], uint32_t a0, uint32_t a1, uint32_t a2, uint32_t a3, uint32_t b0, uint32_t b1) {
  asm volatile("mma.sync.aligned.m16n8k16.row.col.f32.bf16.bf16.f32 {%0,%1,%2,%3},{%4,%5,%6,%7},{%8,%9},{%0,%1,%2,%3};"
               : "+f"(c[0]), "+f"(c[1]), "+f"(c[2]), "+f"(c[3]) : "r"(a0), "r"(a1), "r"(a2), "r"(a3), "r"(b0), "r"(b1));
}
#define CONV_FENCE __syncwarp()
__device__ __forceinline__ void wgmma_n112_tb(float (&d)[56], uint64_t da, uint64_t db, int acc) {
  asm volatile("{ .reg .pred p; setp.ne.b32 p, %58, 0;\n"
    "wgmma.mma_async.sync.aligned.m64n112k16.f32.bf16.bf16 "
    "{%0,%1,%2,%3,%4,%5,%6,%7,%8,%9,%10,%11,%12,%13,%14,%15,"
    "%16,%17,%18,%19,%20,%21,%22,%23,%24,%25,%26,%27,%28,%29,%30,%31,"
    "%32,%33,%34,%35,%36,%37,%38,%39,%40,%41,%42,%43,%44,%45,%46,%47,"
    "%48,%49,%50,%51,%52,%53,%54,%55},"
    " %56, %57, p, 1, 1, 0, 1; }"
    : "+f"(d[0]),"+f"(d[1]),"+f"(d[2]),"+f"(d[3]),"+f"(d[4]),"+f"(d[5]),"+f"(d[6]),"+f"(d[7]),
      "+f"(d[8]),"+f"(d[9]),"+f"(d[10]),"+f"(d[11]),"+f"(d[12]),"+f"(d[13]),"+f"(d[14]),"+f"(d[15]),
      "+f"(d[16]),"+f"(d[17]),"+f"(d[18]),"+f"(d[19]),"+f"(d[20]),"+f"(d[21]),"+f"(d[22]),"+f"(d[23]),
      "+f"(d[24]),"+f"(d[25]),"+f"(d[26]),"+f"(d[27]),"+f"(d[28]),"+f"(d[29]),"+f"(d[30]),"+f"(d[31]),
      "+f"(d[32]),"+f"(d[33]),"+f"(d[34]),"+f"(d[35]),"+f"(d[36]),"+f"(d[37]),"+f"(d[38]),"+f"(d[39]),
      "+f"(d[40]),"+f"(d[41]),"+f"(d[42]),"+f"(d[43]),"+f"(d[44]),"+f"(d[45]),"+f"(d[46]),"+f"(d[47]),
      "+f"(d[48]),"+f"(d[49]),"+f"(d[50]),"+f"(d[51]),"+f"(d[52]),"+f"(d[53]),"+f"(d[54]),"+f"(d[55])
    : "l"(da), "l"(db), "r"(acc));
}
__device__ __forceinline__ void wgmma_n112(float (&d)[56], uint64_t da, uint64_t db, int acc) {
  asm volatile("{ .reg .pred p; setp.ne.b32 p, %58, 0;\n"
    "wgmma.mma_async.sync.aligned.m64n112k16.f32.bf16.bf16 "
    "{%0,%1,%2,%3,%4,%5,%6,%7,%8,%9,%10,%11,%12,%13,%14,%15,"
    "%16,%17,%18,%19,%20,%21,%22,%23,%24,%25,%26,%27,%28,%29,%30,%31,"
    "%32,%33,%34,%35,%36,%37,%38,%39,%40,%41,%42,%43,%44,%45,%46,%47,"
    "%48,%49,%50,%51,%52,%53,%54,%55},"
    " %56, %57, p, 1, 1, 0, 0; }"
    : "+f"(d[0]),"+f"(d[1]),"+f"(d[2]),"+f"(d[3]),"+f"(d[4]),"+f"(d[5]),"+f"(d[6]),"+f"(d[7]),
      "+f"(d[8]),"+f"(d[9]),"+f"(d[10]),"+f"(d[11]),"+f"(d[12]),"+f"(d[13]),"+f"(d[14]),"+f"(d[15]),
      "+f"(d[16]),"+f"(d[17]),"+f"(d[18]),"+f"(d[19]),"+f"(d[20]),"+f"(d[21]),"+f"(d[22]),"+f"(d[23]),
      "+f"(d[24]),"+f"(d[25]),"+f"(d[26]),"+f"(d[27]),"+f"(d[28]),"+f"(d[29]),"+f"(d[30]),"+f"(d[31]),
      "+f"(d[32]),"+f"(d[33]),"+f"(d[34]),"+f"(d[35]),"+f"(d[36]),"+f"(d[37]),"+f"(d[38]),"+f"(d[39]),
      "+f"(d[40]),"+f"(d[41]),"+f"(d[42]),"+f"(d[43]),"+f"(d[44]),"+f"(d[45]),"+f"(d[46]),"+f"(d[47]),
      "+f"(d[48]),"+f"(d[49]),"+f"(d[50]),"+f"(d[51]),"+f"(d[52]),"+f"(d[53]),"+f"(d[54]),"+f"(d[55])
    : "l"(da), "l"(db), "r"(acc));
}
__device__ __forceinline__ void wgmma_n64_tb(float (&d)[32], uint64_t da, uint64_t db, int acc) {
  asm volatile("{ .reg .pred p; setp.ne.b32 p, %34, 0;\n"
    "wgmma.mma_async.sync.aligned.m64n64k16.f32.bf16.bf16 "
    "{%0,%1,%2,%3,%4,%5,%6,%7,%8,%9,%10,%11,%12,%13,%14,%15,"
    "%16,%17,%18,%19,%20,%21,%22,%23,%24,%25,%26,%27,%28,%29,%30,%31},"
    " %32, %33, p, 1, 1, 0, 1; }"
    : "+f"(d[0]),"+f"(d[1]),"+f"(d[2]),"+f"(d[3]),"+f"(d[4]),"+f"(d[5]),"+f"(d[6]),"+f"(d[7]),
      "+f"(d[8]),"+f"(d[9]),"+f"(d[10]),"+f"(d[11]),"+f"(d[12]),"+f"(d[13]),"+f"(d[14]),"+f"(d[15]),
      "+f"(d[16]),"+f"(d[17]),"+f"(d[18]),"+f"(d[19]),"+f"(d[20]),"+f"(d[21]),"+f"(d[22]),"+f"(d[23]),
      "+f"(d[24]),"+f"(d[25]),"+f"(d[26]),"+f"(d[27]),"+f"(d[28]),"+f"(d[29]),"+f"(d[30]),"+f"(d[31])
    : "l"(da), "l"(db), "r"(acc));
}

struct Params {
  const __nv_bfloat16 *x, *k, *v, *shift_k, *ssm_k, *ssm_D, *w_in, *w_sp, *b_sp, *w_out;
  __nv_bfloat16* out;
  int zero;
};

__device__ __forceinline__ uint32_t hslot(int s) {
  return s < 3 ? (s + 1) * HB : s == 3 ? 11 * PAGE : s == 4 ? 0u : CONV_OFF + (s - 5) * HB;
}

__device__ __forceinline__ unsigned tag8(unsigned tag) { return tag % 255u + 1u; }

__device__ __forceinline__ void spin_cycles(int n) {
  const long long t = clock64();
  while (clock64() - t < n) {}
}

__device__ __forceinline__ void cs_part(uint32_t src, int cc, int lane, ulonglong2* dst, unsigned tag) {
  const int c7 = cc < 7 ? cc : 0, l16 = lane & 15;
  float c[8];
#pragma unroll
  for (int e = 0; e < 8; e++) c[e] = 0.f;
#pragma unroll
  for (int n = 0; n < 4; n++) {
    const uint4 v = lds128(src + (16 * n + l16) * 112 + c7 * 16);
    c[0] += bf_lo(v.x); c[1] += bf_hi(v.x); c[2] += bf_lo(v.y); c[3] += bf_hi(v.y);
    c[4] += bf_lo(v.z); c[5] += bf_hi(v.z); c[6] += bf_lo(v.w); c[7] += bf_hi(v.w);
  }
#pragma unroll
  for (int o = 4; o; o >>= 1) {
#pragma unroll
    for (int e = 0; e < o; e++) {
      const float keep = (lane & o) ? c[e + o] : c[e], give = (lane & o) ? c[e] : c[e + o];
      c[e] = keep + __shfl_xor_sync(0xffffffffu, give, o);
    }
  }
  c[0] += __shfl_xor_sync(0xffffffffu, c[0], 8);
  if (cc < 7 && l16 < 8) st_rlx64((unsigned long long*)dst + 8 * c7 + l16, ((unsigned long long)tag << 32) | __float_as_uint(c[0]));
}

__device__ __forceinline__ void wait_count(const unsigned* p, unsigned target) {
  unsigned a = ld_rlx(p);
  spin_cycles(230);
  unsigned b = ld_rlx(p);
  spin_cycles(230);
  unsigned c = ld_rlx(p);
  int it = 0;
  while (true) {
    if ((int)(a - target) >= 0) break;
    a = ld_rlx(p);
    if ((int)(b - target) >= 0) break;
    b = ld_rlx(p);
    if ((int)(c - target) >= 0) break;
    c = ld_rlx(p);
    SPIN_GUARD(it, 5);
  }
}

__device__ __forceinline__ unsigned now_ns() {
  unsigned t; asm volatile("mov.u32 %0, %globaltimer_lo;" : "=r"(t)); return t;
}
__device__ __forceinline__ uint2 ld_rlx2(const unsigned* p) {
  unsigned long long v; asm volatile("ld.relaxed.gpu.global.b64 %0, [%1];" : "=l"(v) : "l"(p) : "memory");
  return make_uint2((unsigned)v, (unsigned)(v >> 32));
}
__device__ __forceinline__ unsigned wait_count2(const unsigned* p, unsigned target) {
  uint2 a = ld_rlx2(p);
  spin_cycles(230);
  uint2 b = ld_rlx2(p);
  spin_cycles(230);
  uint2 c = ld_rlx2(p);
  int it = 0;
  while (true) {
    if ((int)(a.x - target) >= 0) return a.y;
    a = ld_rlx2(p);
    if ((int)(b.x - target) >= 0) return b.y;
    b = ld_rlx2(p);
    if ((int)(c.x - target) >= 0) return c.y;
    c = ld_rlx2(p);
    SPIN_GUARD(it, 5);
  }
  return 0;
}

__global__ void __cluster_dims__(2, 1, 1) __launch_bounds__(512, 1)
fused_kernel(const __grid_constant__ CUtensorMap mX, const __grid_constant__ CUtensorMap mWin,
             const __grid_constant__ CUtensorMap mWsp, const __grid_constant__ CUtensorMap mWout,
             const __grid_constant__ CUtensorMap mY, const __grid_constant__ CUtensorMap mOut,
             const __grid_constant__ CUtensorMap mK, const __grid_constant__ CUtensorMap mV,
             const __grid_constant__ CUtensorMap mWh, const __grid_constant__ CUtensorMap mU,
             const __grid_constant__ CUtensorMap mWpf, const __grid_constant__ CUtensorMap mWcs,
             const __grid_constant__ CUtensorMap mXq, const __grid_constant__ CUtensorMap mWin48, const Params P) {
  extern __shared__ __align__(1024) unsigned char smem_raw[];
  const uint32_t sb = smem_u32(smem_raw);
  const int warp = __shfl_sync(0xffffffffu, threadIdx.x >> 5, 0);
  const int lane = threadIdx.x & 31;
  int grp, mem;
  const int rank = blockIdx.x & 1;
  {
    const int c = blockIdx.x >> 1, t = c < 4 ? 62 + c : c - 4;
    int m;
    if (t < 32) { grp = t & 7; m = t >> 3; }
    else if (t < 60) { grp = 1 + (t - 32) % 7; m = 4 + (t - 32) / 7; }
    else if (t < 62) { grp = -1; m = t - 60; }
    else { grp = 0; m = t - 58; }
    mem = 2 * m + rank;
  }
  const int ti = 4 * (grp >> 1) + ((mem >> 1) & 3);
  const int tj = 4 * (grp & 1) + 2 * (mem >> 3) + (mem & 1);
  const int rho = ti * 8 + tj;
  auto BAR = [&](int n) { return sb + BAR_OFF + n * 8; };
  const int g = lane >> 2, q = lane & 3;
  auto loadX = [&](int n) {
    mbar_expect(BAR(B_FULLX + n), PAGE);
    tma2d(sb + n * PAGE, &mX, 64 * n, 128 * ti, BAR(B_FULLX + n));
  };
  auto loadW = [&](int n) {
    const int c = (n < 8 ? FH_ : 0) + 112 * tj, r = 64 * (n & 7);
    const uint32_t dst = sb + (8 + (n & 3)) * PAGE, bar = BAR((n < 8 ? B_FULLW : B_FULLW2) + (n & 3));
    mbar_expect(bar, HB);
    tma2d(dst, &mWin, c, r, bar);
    tma2d(dst + 8192, &mWin48, c + 64, r, bar);
  };
  if (warp == 8 && grp >= 0) {
    if (lane == 0) {
      mbar_init(BAR(B_FULLX), 1); mbar_init(BAR(B_FULLW), 1);
      TS(40);
      loadX(0); loadW(0);
#pragma unroll
      for (int n = 1; n <= B_FULLKV; n++) if (n != B_FULLW) mbar_init(BAR(n), 1);
      asm volatile("fence.mbarrier_init.release.cluster;" ::: "memory");
    }
    __syncwarp();
    bar_arrive(0, 512);
    if (lane == 0) {
#pragma unroll
      for (int n = 0; n < 4; n++) {
        if (n) { loadX(n); loadW(n); }
        if (n == C_POS) {
          mbar_expect(BAR(B_FULLC), 7168);
          tma2d(sb + 7 * PAGE, &mWh, FH_ + 112 * tj + 56 * (ti & 1), 64 * (ti >> 1), BAR(B_FULLC));
        }
        if (n == C_POS) {
          mbar_expect(BAR(B_FULLXQ), XQ * 2048);
          tma2d(sb + 7 * PAGE + 8192, &mXq, 512 - 64 * XQ, 16 * rho, BAR(B_FULLXQ));
        }
      }
#pragma unroll
      for (int n = 4; n < XLOOK; n++) loadX(n);
    }
    __syncwarp();
  }

  if (grp < 0) {
    constexpr uint32_t CB = 128 * 448;
    unsigned ticket = 0;
    if (threadIdx.x == 480) {
#pragma unroll
      for (int n = 0; n < 4; n++) mbar_init(BAR(n), 1);
      asm volatile("fence.mbarrier_init.release.cluster;" ::: "memory");
      asm volatile("atom.relaxed.gpu.global.add.u32 %0, [%1], 1;" : "=r"(ticket) : "l"(&g_ticket) : "memory");
      sts32(sb + TAG_OFF, ticket / GRID + 1u);
      __nanosleep(HELP_DELAY);
#pragma unroll
      for (int n = 0; n < 4; n++) {
        mbar_expect(BAR(n), CB);
        tma2d(sb + n * CB, &mWcs, 224 * mem, 128 * n, BAR(n));
      }
    }
    bar_sync(0, 512);
    const int cc = threadIdx.x % 28, rg = threadIdx.x / 28;
    float c[8];
#pragma unroll
    for (int e = 0; e < 8; e++) c[e] = 0.f;
#pragma unroll 1
    for (int n = 0; n < 4; n++) {
      mbar_wait(BAR(n), 0);
      if (rg < 16) {
#pragma unroll
        for (int r = 0; r < 8; r++) {
          const uint4 v = lds128(sb + n * CB + (16 * r + rg) * 448 + cc * 16);
          c[0] += bf_lo(v.x); c[1] += bf_hi(v.x); c[2] += bf_lo(v.y); c[3] += bf_hi(v.y);
          c[4] += bf_lo(v.z); c[5] += bf_hi(v.z); c[6] += bf_lo(v.w); c[7] += bf_hi(v.w);
        }
      }
    }
    bar_sync(0, 512);
    if (rg < 16) {
      sts128(sb + rg * 896 + cc * 32, __float_as_uint(c[0]), __float_as_uint(c[1]), __float_as_uint(c[2]), __float_as_uint(c[3]));
      sts128(sb + rg * 896 + cc * 32 + 16, __float_as_uint(c[4]), __float_as_uint(c[5]), __float_as_uint(c[6]), __float_as_uint(c[7]));
    }
    bar_sync(0, 512);
    if (threadIdx.x < 224) {
      float t = 0.f;
#pragma unroll
      for (int r = 0; r < 16; r++) t += __uint_as_float(lds32(sb + r * 896 + threadIdx.x * 4));
      st_rlx64((unsigned long long*)g_cs1 + 224 * mem + threadIdx.x, ((unsigned long long)lds32(sb + TAG_OFF) << 32) | __float_as_uint(t));
    }
    return;
  }

  if (warp < 8) {
    asm volatile("setmaxnreg.inc.sync.aligned.u32 152;");
    const int wg = warp >> 2, w = warp & 3, tid = threadIdx.x & 127;
    bar_sync(0, 512);
    cluster_arrive();
    const int mr = lane & 7, mh = (lane >> 3) & 1, mn = lane >> 4;
    const int row_a = 128 * ti + 64 * wg + 16 * w + g;
    const int myrow = row_a + 8 * (q & 1);
    float acc0[56];
    const uint64_t dA1 = mkdesc(sb + wg * 8192, 16, 1024, 1);
    const uint64_t dB1 = mkdesc(sb + 8 * PAGE, 8192, 1024, 1);
    auto mma1 = [&](int kk, int page) {
      const uint64_t a = dA1 + (uint64_t)(kk * (PAGE >> 4)), b = dB1 + (uint64_t)(page * (PAGE >> 4));
      wg_fence();
#pragma unroll
      for (int k = 0; k < 4; k++) wgmma_n112_tb(acc0, a + 2 * k, b + 128 * k, (kk | k) != 0);
      wg_commit();
    };
    float nmu[2], ha[2];
    float s0 = 0.f, s1 = 0.f, ss0 = 0.f, ss1 = 0.f;
    auto gelu = [&](int pass) {
      const uint32_t csb = sb + CS_OFF + (1 - pass) * 448 + q * 8;
      float ga[2], gb[2];
#pragma unroll
      for (int r = 0; r < 2; r++) {
        ga[r] = 2.f * 0.7978845608028654f * ha[r];
        gb[r] = 8.f * 0.7978845608028654f * 0.044715f * ha[r] * ha[r] * ha[r];
      }
      float t[8];
      uint2 cw0 = lds64(csb), cw1 = lds64(csb + 32);
#pragma unroll
      for (int n = 0; n <= 7; n++) {
        float u[8];
        if (n < 7) {
#pragma unroll
          for (int e = 0; e < 8; e++) {
            const uint2 cw = (e & 4) ? cw1 : cw0;
            acc0[8 * n + e] = fmaf(nmu[(e >> 1) & 1], __uint_as_float((e & 1) ? cw.y : cw.x), acc0[8 * n + e]);
          }
          if (n < 6) {
            const uint32_t a = (csb | (__float_as_uint(acc0[8 * n]) & (uint32_t)P.zero)) + (n + 1) * 64;
            cw0 = lds64(a); cw1 = lds64(a + 32);
          }
#pragma unroll
          for (int e = 0; e < 8; e++)
            u[e] = acc0[8 * n + e] * fmaf(acc0[8 * n + e] * acc0[8 * n + e], gb[(e >> 1) & 1], ga[(e >> 1) & 1]);
        }
        if (n > 0) {
#pragma unroll
          for (int e = 0; e < 8; e++) {
            const float z = fmaf(acc0[8 * n - 8 + e], t[e], acc0[8 * n - 8 + e]);
            acc0[8 * n - 8 + e] = z;
            if (pass == 0) {
              if (e & 2) { s1 += z; ss1 = fmaf(z, z, ss1); } else { s0 += z; ss0 = fmaf(z, z, ss0); }
            }
          }
        }
        if (n < 7) {
#pragma unroll
          for (int e = 0; e < 8; e++) t[e] = tanh_fast(u[e]);
        }
      }
    };
#pragma unroll 1
    for (int kk = 0; kk < 8; kk++) {
      mbar_wait(BAR(B_FULLX + kk), 0);
      if (threadIdx.x == 0) TS(48 + kk);
      mbar_wait(BAR(B_FULLW + (kk & 3)), kk >> 2);
      if (kk == 0 && tid == 0) TS(2);
      mma1(kk, kk & 3);
      if (kk > 0) {
        wg_wait<1>();
        if (tid == 0) {
          mbar_arrive(BAR(B_EMPTYW + ((kk - 1) & 3)));
        }
      }
    }
    ulonglong2 xs = ld_ll(&g_xs[myrow]);
    mbar_wait(BAR(B_TAG), 0);
    const unsigned tag = lds32(sb + TAG_OFF);
    mbar_wait(BAR(B_CS), 0);
    wg_wait<0>();
    if (tid == 0) { mbar_arrive(BAR(B_EMPTYW + 3)); mbar_arrive(BAR(B_P1DONE)); TS(4); }
    {
      int it = 0;
      while (!ll_ok(xs, tag)) { xs = ld_ll(&g_xs[myrow]); SPIN_GUARD(it, 2); }
    }
#pragma unroll
    for (int r = 0; r < 2; r++) {
      nmu[r] = -__shfl_sync(0xffffffffu, __uint_as_float((unsigned)xs.x), (lane & 28) | r);
      ha[r] = 0.5f * __shfl_sync(0xffffffffu, __uint_as_float((unsigned)xs.y), (lane & 28) | r);
    }
    if (threadIdx.x == 0) TS(39);
    gelu(0);
    float ts_, tss;
    uint32_t z1p[28];
    {
      ts_ = ((q & 1) ? s1 : s0) + __shfl_xor_sync(0xffffffffu, (q & 1) ? s0 : s1, 1);
      tss = ((q & 1) ? ss1 : ss0) + __shfl_xor_sync(0xffffffffu, (q & 1) ? ss0 : ss1, 1);
      ts_ += __shfl_xor_sync(0xffffffffu, ts_, 2);
      tss += __shfl_xor_sync(0xffffffffu, tss, 2);
    }
    if (q < 2)
      st_rlx64(&g_ln[ti * 1024 + tj * 128 + (myrow & 127)],
               ((unsigned long long)((__float_as_uint(tss) & ~255u) | tag8(tag)) << 32) | __float_as_uint(ts_));
    __syncwarp();
    if (lane == 0) mbar_arrive(BAR(B_LNST));
    if (threadIdx.x == 0) TS(6);
#pragma unroll
    for (int c = 0; c < 28; c++) z1p[c] = pack_bf_v(acc0[2 * c], acc0[2 * c + 1]);
    uint32_t xr[16];
#pragma unroll
    for (int n = 0; n < 8; n += 2)
      ldsm4(sb + tj * PAGE + (64 * wg + 16 * w + 8 * mh + mr) * 128 + (((n + mn) ^ mr) << 4), xr[2 * n], xr[2 * n + 1], xr[2 * n + 2], xr[2 * n + 3]);
    auto step2 = [&](int kk) {
      mbar_wait(BAR(B_FULLW2 + (kk & 3)), kk >> 2);
      if (kk == 0 && tid == 0) TS(3);
      mma1(kk, kk & 3);
      if (kk > 0) {
        wg_wait<1>();
        if (tid == 0) {
          if (kk < (LL_STEP1 == 4 ? 4 : 5)) mbar_arrive(BAR(B_EMPTYW + kk - 1));
          if (kk == 2) mbar_arrive(BAR(B_X01));
        }
      }
    };
#pragma unroll 1
    for (int kk = 0; kk < LL_STEP1; kk++) step2(kk);
    {
      if (LL_STEP1 == 4) {
        wg_wait<0>();
        if (tid == 0) mbar_arrive(BAR(B_EMPTYW + 3));
      }
      mbar_wait(BAR(B_LN), 0);
      const uint32_t t0 = lds32(sb + LN_OFF + (64 * wg + 16 * w + g) * 4), t1 = lds32(sb + LN_OFF + (64 * wg + 16 * w + g + 8) * 4);
      const uint32_t na0 = __byte_perm(t0, t0, 0x1010), nb0 = __byte_perm(t0, t0, 0x3232);
      const uint32_t na1 = __byte_perm(t1, t1, 0x1010), nb1 = __byte_perm(t1, t1, 0x3232);
      if (threadIdx.x == 0) TS(7);
      const uint32_t st0 = sb + wg * PAGE + (8 * mn + mr) * 128 + (((2 * w + mh) ^ mr) << 4);
#pragma unroll
      for (int n = 0; n < 14; n += 2)
        stsm4t(st0 + n * 1024, bfma2(z1p[2 * n], na0, nb0), bfma2(z1p[2 * n + 1], na1, nb1),
               bfma2(z1p[2 * n + 2], na0, nb0), bfma2(z1p[2 * n + 3], na1, nb1));
      fence_async_smem();
      __syncwarp();
      if (lane == 0) mbar_arrive(BAR(B_ZST + wg));
      if (threadIdx.x == 0) TS(8);
    }
#pragma unroll 1
    for (int kk = LL_STEP1; kk < 8; kk++) step2(kk);
    wg_wait<0>();
    if (tid == 0) { mbar_arrive(BAR(B_G1DONE)); TS(5); }
    mbar_wait(BAR(B_CS + 1), 0);
    if (threadIdx.x == 0) TS(63);
    gelu(1);
#pragma unroll
    for (int c = 0; c < 28; c++) z1p[c] = pack_bf(acc0[2 * c], acc0[2 * c + 1]);
    if (tid == 0) mbar_arrive(BAR(B_Z1DONE));
    if (threadIdx.x == 0) TS(10);
    const float rs_a = 2.f * ha[0], rs_b = 2.f * ha[1], nm_a = nmu[0] * rs_a, nm_b = nmu[1] * rs_b;
    const float bs_a = ha[0] * __bfloat162float(P.b_sp[row_a]), bs_b = ha[1] * __bfloat162float(P.b_sp[row_a + 8]);
    {
      {
        const uint64_t dA = mkdesc(sb + 2 * PAGE + wg * 8192, 16, 1024, 1);
        const uint64_t dB = mkdesc(sb, 16, 1024, 1);
        int as = 0, ap = 0, bs = 0, bp = 0;
#pragma unroll 1
        for (int s = 0; s < 32; s++) {
          mbar_wait(BAR(B_FULLA + as), ap);
          mbar_wait(BAR(B_FULLB + bs), bp);
          if (s == 0 && tid == 0) TS(11 + wg);
          if (s == 3 && threadIdx.x == 0) mbar_arrive(BAR(B_G2RUN));
          const uint64_t a = dA + (uint64_t)(as * (PAGE >> 4)), b = dB + (uint64_t)((bs < 2 ? bs : bs + 6) * (PAGE >> 4));
          wg_fence();
#pragma unroll
          for (int k = 0; k < 4; k++) wgmma_n112(acc0, a + 2 * k, b + 2 * k, (s | k) != 0);
          wg_commit();
          if (s > 0 && !(CONV_E1 > CONV_E0 && s == PAUSE_STEP + 1)) {
            wg_wait<1>();
            if (tid == 0) {
              mbar_arrive(BAR(B_DONE2 + (as == 0 ? 5 : as - 1)));
              if (SKEW && wg == 0 && s == PAUSE_STEP + 1 + SKEW) mbar_arrive(BAR(B_SKEW));
            }
          }
          if (CONV_E1 > CONV_E0 && s == PAUSE_STEP) {
            wg_wait<0>();
            if (tid == 0) { mbar_arrive(BAR(B_DONE2 + as)); mbar_arrive(BAR(B_PAUSE)); }
            mbar_wait(BAR(B_RESUME), 0);
            if (SKEW && wg == 1) mbar_wait(BAR(B_SKEW), 0);
          }
          if (++as == 6) { as = 0; ap ^= 1; }
          if (++bs == 5) { bs = 0; bp ^= 1; }
        }
        wg_wait<0>();
        if (tid == 0) { mbar_arrive(BAR(B_DONE2 + 1)); if (!RESUME_LATE) mbar_arrive(BAR(B_G2DONE)); TS(13 + wg); }
        if (wg == 0) mbar_wait(BAR(B_DONE2), 1);
      }
      {
        const uint32_t st0 = sb + wg * 11 * PAGE + (2 * w + mh) * 1792 + mn * 128 + mr * 16;
#pragma unroll
        for (int n = 0; n < 14; n += 2) {
          uint32_t r[4];
#pragma unroll
          for (int e = 0; e < 4; e++) {
            const float bb = (e & 1) ? bs_b : bs_a, hh = ha[e & 1];
            r[e] = bmul2(z1p[2 * n + e], pack_bf(fmaf(acc0[4 * n + 2 * e], hh, bb), fmaf(acc0[4 * n + 2 * e + 1], hh, bb)));
          }
          stsm4(st0 + n * 128, r[0], r[1], r[2], r[3]);
        }
      }
      float acc3[32];
      {
        fence_async_smem();
        __syncwarp();
        if (lane == 0) mbar_arrive(BAR(B_HST + wg));
        if (tid == 0) { if (RESUME_LATE) mbar_arrive(BAR(B_G2DONE)); if (wg == 0) TS(15); }
        mbar_wait(BAR(B_CONVMMA), 0);
        mbar_wait(BAR(B_FULLWO), 0);
        const uint64_t dA = mkdesc(sb, 128, 1792, 0);
        const uint64_t dB = mkdesc(sb + 4 * PAGE, 8192, 1024, 1);
        auto mma3 = [&](uint32_t aoff, int c, int first) {
          const uint64_t a = dA + (uint64_t)(aoff >> 4), b = dB + (uint64_t)(c * (112 * 128 >> 4));
          wg_fence();
#pragma unroll
          for (int k = 0; k < 7; k++) wgmma_n64_tb(acc3, a + 16 * k, b + 128 * k, !(first && k == 0));
          wg_commit();
        };
        cluster_wait();
        auto step3 = [&](int c) {
          const int n = 2 * c + wg;
          mbar_wait(BAR(B_FULLH + n), 0);
          if (c == 0 && tid == 0) TS(19 + wg);
          mma3(hslot(n < 7 ? n : n < 14 ? n - 7 : n - 14), c, c == 0);
          if (c > 0) {
            wg_wait<1>();
            if (tid < 2 && n - 2 < 9) mbar_arrive_cta(BAR(B_DONEH + n - 2), tid);
            if (tid == 0 && c == Y_STEP) mbar_arrive(BAR(B_WOFREE));
          }
        };
#pragma unroll 1
        for (int c = 0; c < RES_STEP - (RES_STAG ? 1 - wg : 0); c++) step3(c);
        const uint32_t ly = sb + 4 * PAGE + wg * 8192 + (8 * mn + mr) * 128 + (((2 * w + mh) ^ mr) << 4);
        const uint32_t stg = sb + hslot(5 + wg) + w * 2048;
        const uint32_t so = stg + (8 * mh + mr) * 128;
        {
          const int yr = tid >> 1;
          const uint32_t ya = sb + 4 * PAGE + wg * 8192 + yr * 128;
          for (int it = 0;; it++) {
            mbar_wait(BAR(B_FULLY + wg), it & 1);
            const uint32_t v0 = lds32(ya + (((4 * (tid & 1)) ^ (yr & 7)) << 4)), v1 = lds32(ya + (((4 * (tid & 1) + 2) ^ (yr & 7)) << 4));
            if (bar_all(1 + wg, 128, (((v0 ^ tag) | (v1 ^ tag)) & 1u) == 0)) break;
            if (tid == 0) {
              fence_async_smem();
              mbar_expect(BAR(B_FULLY + wg), 8192);
              tma2d(sb + 4 * PAGE + wg * 8192, &mY, 128 * ti + 64 * wg, 64 * tj, BAR(B_FULLY + wg));
            }
            if (it > 20000) break;
          }
        }
        if (threadIdx.x == 0) TS(42);
        float res[32];
#pragma unroll
        for (int n = 0; n < 8; n += 2) {
          uint32_t y[4];
          ldsm4t(ly + n * 1024, y[0], y[1], y[2], y[3]);
#pragma unroll
          for (int e = 0; e < 4; e++) {
            const float rs = (e & 1) ? rs_b : rs_a, nm = (e & 1) ? nm_b : nm_a;
            const float x0 = bf_lo(xr[2 * n + e]), x1 = bf_hi(xr[2 * n + e]);
            res[4 * n + 2 * e] = fmaf(fmaf(x0, rs, nm), bf_lo(y[e]), x0);
            res[4 * n + 2 * e + 1] = fmaf(fmaf(x1, rs, nm), bf_hi(y[e]), x1);
          }
        }
#pragma unroll
        for (int n = 0; n < 32; n++) asm volatile("" : "+f"(res[n]));
        if (threadIdx.x == 0) TS(34);
#pragma unroll 1
        for (int c = RES_STEP - (RES_STAG ? 1 - wg : 0); c < 8; c++) step3(c);
        wg_wait<0>();
        if (tid == 0) TS(21 + wg);
#pragma unroll
        for (int n = 0; n < 8; n += 2) {
          uint32_t r[4];
#pragma unroll
          for (int e = 0; e < 4; e++)
            r[e] = pack_bf(res[4 * n + 2 * e] + acc3[4 * n + 2 * e], res[4 * n + 2 * e + 1] + acc3[4 * n + 2 * e + 1]);
          stsm4(so + (((n + mn) ^ mr) << 4), r[0], r[1], r[2], r[3]);
        }
        {
          __syncwarp();
#pragma unroll
          for (int n = 0; n < 4; n++) {
            const int r = 4 * n + (lane >> 3);
            const uint4 v = lds128(stg + r * 128 + (((lane ^ r) & 7) << 4));
            *(uint4*)(P.out + (size_t)(128 * ti + 64 * wg + 16 * w + r) * D_ + 64 * tj + 8 * (lane & 7)) = v;
          }
          if (lane == 0) {
            if (w == 0) TS(23 + wg);
          }
        }
      }
    }
  } else if (warp < 12) {
    asm volatile("setmaxnreg.inc.sync.aligned.u32 152;");
    const int w = warp - 8;
    const uint32_t cb = sb + CONV_OFF + w * CONV_W;
    const int ch = 4 * rho + w;
    if (w) bar_arrive(0, 512);
    bar_sync(7, 256);
    cluster_arrive();
    const int tid = threadIdx.x & 127;
    uint4 tapw[4];
#pragma unroll
    for (int m = 0; m < 4; m++) tapw[m] = __ldg((const uint4*)(P.shift_k + (128 * (rho & 3) + 32 * w + 8 * m + 2 * q) * 4));
    mbar_wait(BAR(B_TAG), 0);
    const unsigned tag = lds32(sb + TAG_OFF);
    {
      const int r = 4 * w + (lane >> 3), rb = 16 * tj + r;
      float s = 0.f, m2 = 0.f;
      auto xsum = [&](uint32_t a) {
        const uint4 v = lds128(a);
        const uint32_t ww[4] = {v.x, v.y, v.z, v.w};
#pragma unroll
        for (int e = 0; e < 4; e++) {
          const float d0 = bf_lo(ww[e]), d1 = bf_hi(ww[e]);
          s += d0 + d1; m2 = fmaf(d0, d0, fmaf(d1, d1, m2));
        }
      };
      mbar_wait(BAR(B_FULLC), 0);
      cs_part(sb + 7 * PAGE, 2 * w + (lane >> 4), lane, &g_cs[(tj * 8 + (ti >> 1)) * 64 + 28 * (ti & 1)], tag);
      mbar_wait(BAR(B_FULLXQ), 0);
#pragma unroll
      for (int n = 0; n < XQ; n++) xsum(sb + 7 * PAGE + 8192 + r * XQ * 128 + n * 128 + (lane & 7) * 16);
      __syncwarp();
      if (lane == 0) mbar_arrive(BAR(B_CFREE));
      if (tid == 0) TS(45);
#pragma unroll 1
      for (int kk = 0; kk < 8 - XQ; kk++) {
        mbar_wait(BAR(B_FULLX + kk), 0);
        xsum(sb + kk * PAGE + rb * 128 + (((lane ^ rb) & 7) << 4));
      }
#pragma unroll
      for (int o = 1; o < 8; o <<= 1) { s += __shfl_xor_sync(0xffffffffu, s, o); m2 += __shfl_xor_sync(0xffffffffu, m2, o); }
      const float mu = s * (1.f / D_);
      if ((lane & 7) == 0) st_ll(&g_xs[16 * rho + r], mu, rsqrtf(fmaxf(m2 * (1.f / D_) - mu * mu, 0.f) + 1e-5f), tag);
      if (tid == 0) TS(1);
    }
    {
      int it = 0;
      mbar_wait(BAR(B_P1DONE), 0);
      ulonglong2 xs = ld_ll(&g_xs[128 * ti + tid]);
      while (!ll_ok(xs, tag)) { xs = ld_ll(&g_xs[128 * ti + tid]); SPIN_GUARD(it, 2); }
      const float hq = 0.5f * __uint_as_float((unsigned)xs.y);
      mbar_wait(BAR(B_LNST), 0);
      spin_cycles(LN_DELAY);
      if (LN_AFTER_KV) mbar_wait(BAR(B_FULLKV), 0);
      const unsigned long long* ln = &g_ln[ti * 1024 + tid];
      float ps, pss;
      unsigned long long lv[8], lw[8];
      auto ln_load = [&](unsigned long long (&v)[8]) {
#pragma unroll
        for (int o = 0; o < 8; o++) v[o] = ld_rlx64(ln + o * 128);
      };
      auto ln_sum = [&](const unsigned long long (&v)[8]) {
        bool ok = true;
        ps = 0.f; pss = 0.f;
#pragma unroll
        for (int o = 0; o < 8; o++) {
          ok = ok && ((unsigned)(v[o] >> 32) & 255u) == tag8(tag);
          ps += __uint_as_float((unsigned)v[o]); pss += __uint_as_float((unsigned)(v[o] >> 32) & ~255u);
        }
        return ok;
      };
      ln_load(lv);
      if (LN_GAP) { spin_cycles(LN_GAP); ln_load(lw); }
      while (true) {
        if (ln_sum(lv)) break;
        ln_load(lv);
        if (LN_GAP) {
          if (ln_sum(lw)) break;
          ln_load(lw);
        }
        SPIN_GUARD(it, 3);
      }
      const float m = ps * (1.f / FH_);
      const float rz = hq * rsqrtf(hq * hq * fmaxf(pss * (1.f / FH_) - m * m, 0.f) + 1e-5f);
      sts32(sb + LN_OFF + tid * 4, pack_bf(rz, -m * rz));
      mbar_wait(BAR(B_X01), 0);
      __syncwarp();
      if (lane == 0) mbar_arrive(BAR(B_LN));
      if (tid == 0) TS(47);
    }
    {
      mbar_wait(BAR(B_FULLKV), 0);
      if (KV_WAIT) mbar_wait(BAR(KV_WAIT), 0);

      const int h = w >> 1, cb0 = 4 * (w & 1) + (lane >> 3), lr = (lane & 7) ^ 1;
      uint32_t tap[4][4];
#pragma unroll
      for (int m = 0; m < 4; m++) {
        const uint4 t = tapw[m];
        tap[m][0] = __byte_perm(t.x, t.z, 0x5410); tap[m][1] = __byte_perm(t.x, t.z, 0x7632);
        tap[m][2] = __byte_perm(t.y, t.w, 0x5410); tap[m][3] = __byte_perm(t.y, t.w, 0x7632);
      }
      uint32_t kv[8][4];
#pragma unroll
      for (int b = 0; b < 8; b++) {
        uint32_t kk[4][4], vv[4];
#pragma unroll
        for (int s = 0; s < 4; s++) {
          const int row = 8 * b + lr + s;
          ldsm4(sb + CONV_OFF + 16384 + h * 8576 + row * 128 + (((cb0 ^ (row + 3 * h)) & 7) << 4), kk[s][0], kk[s][1], kk[s][2], kk[s][3]);
        }
        ldsm4(sb + CONV_OFF + h * 8192 + (8 * b + lr) * 128 + (((cb0 ^ lr) & 7) << 4), vv[0], vv[1], vv[2], vv[3]);
#pragma unroll
        for (int m = 0; m < 4; m++) {
          uint32_t a = bmul2(kk[0][m], tap[m][3]);
          a = badd2(a, bmul2(kk[1][m], tap[m][2]));
          a = badd2(a, bmul2(kk[2][m], tap[m][1]));
          a = badd2(a, bmul2(kk[3][m], tap[m][0]));
          kv[b][m] = bmul2(a, vv[m]);
        }
      }
      bar_sync(6, 128);
#pragma unroll
      for (int b = 0; b < 8; b++)
        stsm4t(sb + CONV_OFF + (32 * w + lane) * 128 + (((b ^ lane) & 7) << 4), kv[b][0], kv[b][1], kv[b][2], kv[b][3]);
      fence_async_smem();
      __syncwarp();
      if (lane == 0) mbar_arrive(BAR(B_KVC));
      if (tid == 0) TS(58);
    }
    {
      mbar_wait(BAR(B_USTG), 0);
      if (lane < 14) sts128(cb + lane * 16, 0, 0, 0, 0);
      else if (lane < 16) sts128(cb + 4320 + (lane - 14) * 16, 0, 0, 0, 0);
      __syncwarp();
    }
    cluster_wait();
    const float dskip = __bfloat162float(P.ssm_D[ch]);
    mbar_wait(BAR(B_FULLU), 0);
    if (w == 0 && lane == 0) TS(27);
    float acc[16][4];
#pragma unroll
    for (int n = 0; n < 16; n++) { acc[n][0] = acc[n][1] = acc[n][2] = acc[n][3] = 0.f; }
    if (lane == 0) {
      const uint32_t k01 = lds32(cb + 4352);
      sts32(cb + 4352, pack_bf(bf_lo(k01) + dskip, bf_hi(k01)));
    }
    __syncwarp();
    uint32_t ub = cb + 224 + (8 * g + 2 * q) * 4;
    uint32_t kb = cb + 4352 + (g - 2 * q) * 4;
    struct AF { uint32_t a0, a1, a2, a3; };
    auto ldA = [&](uint32_t p) {
      const uint32_t W0 = lds32(p - 8), W1 = lds32(p - 4), W2 = lds32(p);
      AF r; r.a0 = __byte_perm(W1, W2, 0x5432); r.a1 = W2; r.a2 = __byte_perm(W0, W1, 0x5432); r.a3 = W1;
      return r;
    };
    uint2 B[16];
#pragma unroll
    for (int n = 0; n < 16; n++) B[n] = lds64(ub + n * 256);
    AF a = ldA(kb), c = ldA(kb + 15 * 256);
    mbar_wait(BAR(B_G1DONE), 0);
    if (w == 0 && lane == 0) TS(61);
#pragma unroll 1
    for (int e = 0; e < 8; e++) {
      if (e == CONV_E0 && CONV_E1 > CONV_E0) mbar_wait(BAR(B_PAUSE), 0);
      if (e == CONV_E1) {
        if (lane == 0) { mbar_arrive(BAR(B_RESUME)); if (w == 0) TS(31); }
        mbar_wait(BAR(B_G2DONE), 0);
        if (w == 0 && lane == 0) TS(28);
      }
#pragma unroll
      for (int p = 0; p < 8; p++) {
        const uint32_t pa = p < 7 ? kb + (p + 1) * 256 : kb + 32, pc = p < 7 ? kb + (14 - p) * 256 : kb + 32 + 15 * 256;
        mma16816(acc[15], a.a0, a.a1, a.a2, a.a3, B[15 - p].x, B[15 - p].y);
        B[15 - p] = lds64(ub - 32 + (15 - p) * 256);
        const uint32_t W0 = lds32(pa - 8), W1 = lds32(pa - 4), W2 = lds32(pa);
#pragma unroll
        for (int n = 14; n >= 8; n--) mma16816(acc[n], a.a0, a.a1, a.a2, a.a3, B[n - p].x, B[n - p].y);
        CONV_FENCE;
        const int l2 = p == 0 ? 5 : p == 1 ? 4 : p < 4 ? 3 : p == 4 ? 2 : p < 7 ? 1 : 0, l1 = 8 - p - l2;
#pragma unroll
        for (int n = 7; n > 7 - l1; n--) mma16816(acc[n], a.a0, a.a1, a.a2, a.a3, B[n - p].x, B[n - p].y);
        AF an; an.a0 = __byte_perm(W1, W2, 0x5432); an.a1 = W2; an.a2 = __byte_perm(W0, W1, 0x5432); an.a3 = W1;
        const uint32_t V0 = lds32(pc - 8), V1 = lds32(pc - 4), V2 = lds32(pc);
#pragma unroll
        for (int m = 15; m >= 15 - p; m--) {
          mma16816(acc[m], c.a0, c.a1, c.a2, c.a3, B[m - 15 + p].x, B[m - 15 + p].y);
          if (p == 7) B[m - 8] = lds64(ub - 32 + (m - 8) * 256);
        }
#pragma unroll
        for (int n = 7 - l1; n >= p; n--) mma16816(acc[n], a.a0, a.a1, a.a2, a.a3, B[n - p].x, B[n - p].y);
        CONV_FENCE;
        c.a0 = __byte_perm(V1, V2, 0x5432); c.a1 = V2; c.a2 = __byte_perm(V0, V1, 0x5432); c.a3 = V1;
        a = an;
      }
      ub -= 32; kb += 32;
    }
    __syncwarp();
    if (lane == 0) { mbar_arrive(BAR(B_CONVMMA)); if (w == 0) TS(29); }
    const uint32_t pmask = g == 0 ? ~1u : ~0u, pbit = g == 0 ? tag & 1u : 0u;
#pragma unroll
    for (int n = 0; n < 16; n++) {
#pragma unroll
      for (int c = 0; c < 2; c++) {
        sts32(cb + 4352 + (64 * n + 16 * q + 8 * c + g) * 4, (pack_bf(acc[n][c], acc[n][2 + c]) & pmask) | pbit);
      }
    }
    fence_async_smem();
    bar_sync(6, 128);
    if (tid == 0) {
      TS(44);
#pragma unroll
      for (int r = 0; r < 4; r++) bulk_store(&g_y[(size_t)(4 * rho + r) * (S_ / 8)], sb + CONV_OFF + r * CONV_W + 4352, 4096);
      bulk_commit();
      bulk_wait0();
      TS(43);
      mbar_arrive_cta(BAR(B_CONVFREE), 0);
      mbar_arrive_cta(BAR(B_CONVFREE), 1);
      TS(30);

    }
  } else {
    asm volatile("setmaxnreg.dec.sync.aligned.u32 56;");
    unsigned ticket = 0;
    if (lane == 0) {
      if (warp == 13) asm volatile("atom.relaxed.gpu.global.add.u32 %0, [%1], 1;" : "=r"(ticket) : "l"(&g_ticket) : "memory");
      auto init_range = [&](int lo, int hi) {
#pragma unroll
        for (int n = lo; n < hi; n++) {
          const int cnt = n == B_LNST ? 8
                          : (n == B_CS || n == B_CONVFREE || (n >= B_DONEH && n < B_DONEH + 9) || n == B_PAUSE || n == B_P1DONE || n == B_Z1DONE || n == B_ZSET || n == B_WOFREE || (n >= B_DONE2 && n < B_DONE2 + 6) ||
                             (n >= B_EMPTYW && n < B_EMPTYW + 4) || n == B_G2DONE || n == B_G1DONE || n == B_X01) ? 2
                          : n == B_FULLWO ? 7
                          : (n == B_CFREE || n == B_HFREE || n == B_KVC || n == B_LN || n == B_RESUME || n == B_CONVMMA ||
                             (n >= B_ZST && n < B_HST + 2)) ? 4 : 1;
          mbar_init(BAR(n), cnt);
        }
      };
      if (warp == 12) init_range(15, 34);
      else if (warp == 13) init_range(34, 54);
      else if (warp == 14) init_range(54, 74);
      else init_range(74, B_COUNT);
      asm volatile("fence.mbarrier_init.release.cluster;" ::: "memory");
    }
    __syncwarp();
    bar_arrive(7, 256);
    bar_sync(0, 512);
    cluster_arrive();
    if (warp == 15) {
      if (lane == 0) {
#pragma unroll 1
        for (int n = XLOOK; n < 8; n++) {
          mbar_wait(BAR(B_FULLX + n - XLOOK), 0);
          if (n == 7) { mbar_wait(BAR(B_CFREE), 0); fence_async_smem(); }
          loadX(n);
        }
        const int c0 = 128 * (rho & 3), t0 = 64 * (rho >> 2);
        mbar_wait(BAR(B_TAG), 0);
        const unsigned tag = lds32(sb + TAG_OFF);
        mbar_wait(BAR(PF_GATE), 0);
#pragma unroll 1
        for (int n = 0; n < 6; n++) {
          bulk_prefetch((n < 2 ? P.k : n < 4 ? P.v : P.ssm_k) + (size_t)rho * 8192 + (n & 1) * 4096, 8192);
          spin_cycles(PF_DT);
        }
        mbar_wait(BAR(B_LN), 0);
        tma2d_prefetch(&mWpf, 0, 16 * rho);
        tma2d_prefetch(&mWpf, 256, 16 * rho);
        mbar_wait(BAR(B_KVC), 0);
        mbar_wait(BAR(US_GATE), 0);
#pragma unroll 1
        for (int r = 0; r < 4; r++) {
          tma2d_store(&mU, t0, c0 + 32 * r, sb + CONV_OFF + r * 4096);
          spin_cycles(US_DT);
        }
        bulk_commit();
        bulk_wait0();
        TS(59);
        mbar_arrive(BAR(B_USTG));
        fence_gpu();
        red_inc(&g_cntU[(rho & 3) * 32]);
        TS(25);
        mbar_expect(BAR(B_FULLU), 32768);
#pragma unroll 1
        for (int r = 0; r < 8; r++) {
          if (r == 4) {
            int it = 0;
            while ((int)(ld_rlx(&g_cntU[(rho >> 5) * 32]) - tag * 32u) < 0) { __nanosleep(100); SPIN_GUARD(it, 4); }
          }
          const void* src = r < 4 ? (const void*)(P.ssm_k + (size_t)(4 * rho + r) * S_) : (const void*)&g_u[(size_t)(4 * rho + r - 4) * (S_ / 8)];
          bulk_load(sb + CONV_OFF + (r & 3) * CONV_W + (r < 4 ? 4352 : 224), src, 4096, BAR(B_FULLU));
          spin_cycles(UK_DT);
        }
        TS(26);
        bulk_prefetch(P.w_out + (size_t)(7 * rho) * D_, 7168);
      }
    } else if (warp >= 13) {
      unsigned tag;
      if (warp == 13) {
        tag = __shfl_sync(0xffffffffu, ticket, 0) / GRID + 1u;
        if (lane == 0) { sts32(sb + TAG_OFF, tag); mbar_arrive(BAR(B_TAG)); }
      } else {
        mbar_wait(BAR(B_TAG), 0);
        tag = lds32(sb + TAG_OFF);
      }
      const int cp = 28 * (warp - 13) + (lane < 28 ? lane : 0);
      {
        const ulonglong2* p = &g_cs[tj * 512 + cp];
        mbar_wait(BAR(B_CFREE), 0);
        spin_cycles(CS_DELAY);
        float t0, t1;
        int it = 0;
        while (true) {
          ulonglong2 v[8];
#pragma unroll
          for (int r = 0; r < 8; r++) v[r] = ld_ll(p + r * 64);
          bool ok = true;
          t0 = 0.f; t1 = 0.f;
#pragma unroll
          for (int r = 0; r < 8; r++) {
            ok = ok && ll_ok(v[r], tag);
            t0 += __uint_as_float((unsigned)v[r].x); t1 += __uint_as_float((unsigned)v[r].y);
          }
          if (ok) break;
          SPIN_GUARD(it, 8);
        }
        if (lane < 28) sts64(sb + CS_OFF + 448 + cp * 8, __float_as_uint(t0), __float_as_uint(t1));
        __syncwarp();
        if (lane == 0) { mbar_arrive(BAR(B_CS)); if (warp == 14) TS(56); }
      }
      if (warp == 14) {
        mbar_wait(BAR(B_LNST), 0);
#pragma unroll 1
        for (int h = 0; h < 2; h++) {
          const ulonglong2* p = &g_cs1[56 * tj + 28 * h + (lane < 28 ? lane : 0)];
          ulonglong2 v = ld_ll(p);
          int it = 0;
          while (!ll_ok(v, tag)) { __nanosleep(200); v = ld_ll(p); SPIN_GUARD(it, 9); }
          if (lane < 28) sts64(sb + CS_OFF + (28 * h + lane) * 8, (unsigned)v.x, (unsigned)v.y);
        }
        __syncwarp();
        if (lane == 0) { mbar_arrive(BAR(B_CS + 1)); TS(57); }
      }
      cluster_wait();
      if (lane == 0) {
        const int h = warp - 13;
        mbar_wait(BAR(B_ZST + h), 0);
        bulk_store(&g_z2[(size_t)(tj * 32 + 2 * ti + h) * (HB / 16)], sb + h * PAGE, HB);
        bulk_commit();
        bulk_wait0();
        if (h == 0) TS(38);
        asm volatile("red.relaxed.gpu.global.max.u32 [%0], %1;" ::"l"(&g_cntZ[(tag & 1) * 32 + 1]), "r"(now_ns()) : "memory");
        fence_gpu();
        red_inc(&g_cntZ[(tag & 1) * 32]);
        mbar_arrive(BAR(B_ZSET));
        TS(9);
        mbar_wait(BAR(B_HST + h), 0);
        bulk_store(&g_h[(size_t)(ti * 16 + tj * 2 + h) * (HB / 16)], sb + h * 11 * PAGE, HB);
        bulk_commit();
        bulk_wait0();
        if (h == 0) TS(18);
        if (SKEW) { mbar_arrive_cta(BAR(B_HFREE), 0); mbar_arrive_cta(BAR(B_HFREE), 1); }
        fence_gpu();
        red_inc(&g_cntH[ti * 32 + (SKEW ? 16 * h : 0)]);
        if (h == 0) TS(17); else TS(16);
        wait_count(&g_cntH[ti * 32 + (SKEW ? 16 * h : 0)], tag * (SKEW ? 8u : 16u));
        if (SKEW) mbar_wait(BAR(B_HFREE), 0);
        if (h == 0) TS(33); else TS(36);
        auto loadH = [&](int n) {
          if (n == 5 || n == 6) mbar_wait(BAR(B_CONVFREE), 0);
          if (n >= 7) mbar_wait(BAR(B_DONEH + n - 7), 0);
          mbar_expect(BAR(B_FULLH + n), HB);
          bulk_load_mc(sb + hslot(n % 7) + rank * (HB / 2), &g_h[(size_t)(ti * 16 + n) * (HB / 16) + rank * (HB / 32)], HB / 2,
                       BAR(B_FULLH + n));
        };
        if (h == 0) {
#pragma unroll
          for (int c = 0; c < 8; c++) loadH(2 * c);
        } else {
#pragma unroll
          for (int c = 0; c < 8; c++) loadH(2 * c + 1);
        }
      }
    } else if (lane == 0) {
      asm volatile("{ .reg .pred p; .reg .b64 z; mov.b64 z, 0; setp.ne.u32 p, %0, 0; @p st.global.u32 [z], %0; }" ::"r"(sb & 1023));
      auto loadA = [&](int s, int slot) {
        mbar_expect(BAR(B_FULLA + slot), PAGE);
        tma2d(sb + (2 + slot) * PAGE, &mWsp, 64 * s, 128 * ti, BAR(B_FULLA + slot));
      };
      auto loadB = [&](int s, int slot) {
        mbar_expect(BAR(B_FULLB + slot), HB);
        bulk_load(sb + (slot < 2 ? slot : slot + 6) * PAGE, &g_z2[(size_t)(tj * 32 + s) * (HB / 16)], HB, BAR(B_FULLB + slot));
      };
      auto loadKV = [&]() {
        mbar_expect(BAR(B_FULLKV), 2 * 8576 + 2 * 8192);
#pragma unroll
        for (int h = 0; h < 2; h++) {
          tma2d(sb + CONV_OFF + 16384 + h * 8576, &mK, 128 * (rho & 3) + 64 * h, 64 * (rho >> 2) - 3, BAR(B_FULLKV));
          tma2d(sb + CONV_OFF + h * 8192, &mV, 128 * (rho & 3) + 64 * h, 64 * (rho >> 2), BAR(B_FULLKV));
        }
      };
      auto loadWo = [&](int p) {
        mbar_expect(BAR(B_FULLWO), PAGE);
        tma2d(sb + (4 + p) * PAGE, &mWout, 64 * tj, 128 * p, BAR(B_FULLWO));
      };
#pragma unroll 1
      for (int n = 4; n < 16; n++) {
        mbar_wait(BAR(B_EMPTYW + (n & 3)), ((n >> 2) - 1) & 1);
        loadW(n);
        if (n == KV_POS) loadKV();
        if (n == 11 && KV_POS == 50) { spin_cycles(KV_DELAY); loadKV(); }
      }
      mbar_wait(BAR(B_G1DONE), 0);
      mbar_wait(BAR(B_TAG), 0);
      const unsigned tag = lds32(sb + TAG_OFF);
      if (rho == 0) st_rlx64((unsigned long long*)&g_cntZ[(~tag & 1) * 32], 0ull);
      mbar_wait(BAR(B_ZSET), 0);
#pragma unroll 1
      for (int s = 0; s < A_PRE; s++) loadA(s, s);
      {
        const unsigned t_last = wait_count2(&g_cntZ[(tag & 1) * 32], 256u);
        TS(60);
        int it = 0;
        while ((int)(now_ns() - (t_last + GO_NS)) < 0 && ++it < 100) {}
      }
      TS(32);
#pragma unroll
      for (int s = 0; s < 6; s++) { if (s < 5) loadB(s, s); if (s >= A_PRE) loadA(s, s); }
      {
        int as = 0, ap = 0, bs = 0;
#pragma unroll 1
        for (int s = 0; s < 32; s++) {
          mbar_wait(BAR(B_DONE2 + as), ap);
          if (s + 5 < 32) loadB(s + 5, bs);
          if (s + 6 < 32) loadA(s + 6, as);
          if (s == KV_POS - 100) loadKV();
          if (s >= 26 && s < 30) { loadWo(s - 26); if (s > 26) loadWo(s - 23); }
          if (++as == 6) { as = 0; ap ^= 1; }
          if (++bs == 5) bs = 0;
        }
      }
      mbar_wait(BAR(B_WOFREE), 0);
#pragma unroll
      for (int h = 0; h < 2; h++) {
        mbar_expect(BAR(B_FULLY + h), 8192);
        tma2d(sb + 4 * PAGE + h * 8192, &mY, 128 * ti + 64 * h, 64 * tj, BAR(B_FULLY + h));
      }
      TS(35);
    }
  }
}

typedef CUresult (*EncFn)(CUtensorMap*, CUtensorMapDataType, cuuint32_t, void*, const cuuint64_t*, const cuuint64_t*,
                          const cuuint32_t*, const cuuint32_t*, CUtensorMapInterleave, CUtensorMapSwizzle,
                          CUtensorMapL2promotion, CUtensorMapFloatOOBfill);

CUtensorMap make_map(EncFn enc, const void* p, uint64_t inner, uint64_t outer, uint32_t bi, uint32_t bo,
                     CUtensorMapSwizzle sw = CU_TENSOR_MAP_SWIZZLE_128B) {
  CUtensorMap m;
  cuuint64_t gd[2] = {inner, outer};
  cuuint64_t gs[1] = {inner * 2};
  cuuint32_t bd[2] = {bi, bo};
  cuuint32_t es[2] = {1, 1};
  enc(&m, CU_TENSOR_MAP_DATA_TYPE_BFLOAT16, 2, const_cast<void*>(p), gd, gs, bd, es, CU_TENSOR_MAP_INTERLEAVE_NONE,
      sw, CU_TENSOR_MAP_L2_PROMOTION_L2_128B, CU_TENSOR_MAP_FLOAT_OOB_FILL_NONE);
  return m;
}

}

extern "C" void kernel_launch(void* const* d_in, const int* in_sizes, int n_in, void* d_out, int out_size) {
  (void)in_sizes; (void)n_in; (void)out_size;
  static EncFn enc = nullptr;
  static void *yptr = nullptr, *uptr = nullptr;
  if (!enc) {
    void* f = nullptr;
    cudaDriverEntryPointQueryResult qr;
    cudaGetDriverEntryPoint("cuTensorMapEncodeTiled", &f, cudaEnableDefault, &qr);
    enc = (EncFn)f;
    cudaFuncSetAttribute(fused_kernel, cudaFuncAttributeMaxDynamicSharedMemorySize, SMEM_BYTES);
    cudaGetSymbolAddress(&yptr, g_y);
    cudaGetSymbolAddress(&uptr, g_u);
  }
  Params P;
  P.x = (const __nv_bfloat16*)d_in[0];
  P.k = (const __nv_bfloat16*)d_in[1];
  P.v = (const __nv_bfloat16*)d_in[2];
  P.shift_k = (const __nv_bfloat16*)d_in[3];
  P.ssm_k = (const __nv_bfloat16*)d_in[4];
  P.ssm_D = (const __nv_bfloat16*)d_in[5];
  P.w_in = (const __nv_bfloat16*)d_in[7];
  P.w_sp = (const __nv_bfloat16*)d_in[8];
  P.b_sp = (const __nv_bfloat16*)d_in[9];
  P.w_out = (const __nv_bfloat16*)d_in[10];
  P.zero = 0;
  P.out = (__nv_bfloat16*)d_out;
  const CUtensorMap mX = make_map(enc, P.x, D_, S_, 64, 128);
  const CUtensorMap mWin = make_map(enc, P.w_in, F_, D_, 64, 64);
  const CUtensorMap mWsp = make_map(enc, P.w_sp, S_, S_, 64, 128);
  const CUtensorMap mWout = make_map(enc, P.w_out, D_, FH_, 64, 128);
  const CUtensorMap mY = make_map(enc, yptr, S_, D_, 64, 64);
  const CUtensorMap mOut = make_map(enc, d_out, D_, S_, 64, 16);
  const CUtensorMap mK = make_map(enc, P.k, D_, S_, 64, 67);
  const CUtensorMap mV = make_map(enc, P.v, D_, S_, 64, 64);
  const CUtensorMap mWh = make_map(enc, P.w_in, F_, D_, 56, 64, CU_TENSOR_MAP_SWIZZLE_NONE);
  const CUtensorMap mU = make_map(enc, uptr, S_, D_, 64, 32);
  const CUtensorMap mWpf = make_map(enc, P.w_sp, S_, S_, 256, 16, CU_TENSOR_MAP_SWIZZLE_NONE);
  const CUtensorMap mWcs = make_map(enc, P.w_in, F_, D_, 224, 128, CU_TENSOR_MAP_SWIZZLE_NONE);
  const CUtensorMap mXq = make_map(enc, P.x, D_, S_, 64 * XQ, 16, CU_TENSOR_MAP_SWIZZLE_NONE);
  const CUtensorMap mWin48 = make_map(enc, P.w_in, F_, D_, 48, 64);
  fused_kernel<<<GRID, 512, SMEM_BYTES>>>(mX, mWin, mWsp, mWout, mY, mOut, mK, mV, mWh, mU, mWpf, mWcs, mXq, mWin48, P);
}
```
